```python
import torch

def _softmax(x, axis=-1):
    return torch.softmax(x, dim=axis)
def _gelu(x):
    return torch.nn.functional.gelu(x, approximate="tanh")
def _silu(x):
    return torch.nn.functional.silu(x)
def _sigmoid(x):
    return torch.sigmoid(x)
def _layernorm(x, axis=-1, eps=1e-5):
    m = x.mean(dim=axis, keepdim=True)
    v = x.var(dim=axis, keepdim=True, unbiased=False)
    return (x - m) / torch.sqrt(v + eps)
def _scatter_add(tgt, idx, src, axis=0):
    return tgt.clone().index_add_(axis, idx, src)
def _segment_sum(src, seg, n):
    out = torch.zeros((n,) + src.shape[1:], dtype=src.dtype)
    return out.index_add_(0, seg, src)
def _pad(x, pw):
    flat = tuple(v for pair in reversed(pw) for v in pair)
    return torch.nn.functional.pad(x, flat)

kernel_name = 'standalone__deepnorm__sampling'

def setup_inputs():

    _w = (lambda a: (lambda t: t.to(torch.bfloat16) if t.is_floating_point() else t)(torch.as_tensor(a)))
    B, S, D = 1024, 8, 576
    return {
        "x": _w((lambda *s: torch.randn(*s, dtype=torch.bfloat16) * 0.05)(B, S, D)),
        "f": _w((lambda *s: torch.randn(*s, dtype=torch.bfloat16) * 0.05)(B, S, D)),
        "g": _w((lambda *s: torch.randn(*s, dtype=torch.bfloat16) * 0.05)(D) + 1.0),
        "b": _w((lambda *s: torch.randn(*s, dtype=torch.bfloat16) * 0.2)(D)),
        "alpha": _w(float(2.0)),
    }

def reference(x, f, g, b, alpha):
    return _layernorm(alpha * x + f, axis=-1) * g + b
```

```cpp
#include <cuda_runtime.h>
#include <cuda_bf16.h>
#include <stdint.h>

typedef __nv_bfloat16 bf16;

__device__ __forceinline__ uint4 ldg128(const void* p) {
    uint4 v;
    asm volatile("ld.global.nc.v4.u32 {%0,%1,%2,%3}, [%4];" : "=r"(v.x), "=r"(v.y), "=r"(v.z), "=r"(v.w) : "l"(p));
    return v;
}
__device__ __forceinline__ uint2 ldg64_stream(const void* p) {
    uint2 v;
    asm volatile("ld.global.nc.L1::no_allocate.v2.u32 {%0,%1}, [%2];" : "=r"(v.x), "=r"(v.y) : "l"(p));
    return v;
}
__device__ __forceinline__ void stg64(void* p, uint2 v) {
    asm volatile("st.global.v2.u32 [%0], {%1,%2};" :: "l"(p), "r"(v.x), "r"(v.y) : "memory");
}
__device__ __forceinline__ uint32_t hfma2(uint32_t a, uint32_t b, uint32_t c) {
    uint32_t d; asm("fma.rn.bf16x2 %0, %1, %2, %3;" : "=r"(d) : "r"(a), "r"(b), "r"(c)); return d;
}
__device__ __forceinline__ float lo(uint32_t u) { return __uint_as_float(u << 16); }
__device__ __forceinline__ float hi(uint32_t u) { return __uint_as_float(u & 0xffff0000u); }
__device__ __forceinline__ uint32_t pack(float l, float h) {
    uint32_t d; asm("cvt.rn.bf16x2.f32 %0, %1, %2;" : "=r"(d) : "f"(h), "f"(l)); return d;
}
__device__ __forceinline__ float rbf(float f) { return __bfloat162float(__float2bfloat16_rn(f)); }

constexpr int TPB = 128;

__global__ void __launch_bounds__(TPB, 8)
deepnorm_kernel(const bf16* __restrict__ x, const bf16* __restrict__ f, const bf16* __restrict__ g,
                const bf16* __restrict__ b, const bf16* __restrict__ alpha, bf16* __restrict__ out) {
    __shared__ uint4 sgb[144];
    int t = blockIdx.x * TPB + threadIdx.x;
    int row = t >> 4, l = t & 15;
    const char* px = (const char*)x + (size_t)row * 1152 + l * 8;
    const char* pf = (const char*)f + (size_t)row * 1152 + l * 8;
    char* po = (char*)out + (size_t)row * 1152 + l * 8;
    uint32_t a1 = *(const unsigned short*)alpha;
    uint4 gb[2];
#pragma unroll
    for (int i = 0; i < 2; i++) {
        int k = threadIdx.x + i * TPB;
        if (k < 144) gb[i] = ldg128(k < 72 ? (const char*)g + k * 16 : (const char*)b + (k - 72) * 16);
    }
    uint2 xv[9], fv[9];
#pragma unroll
    for (int j = 0; j < 9; j++) { xv[j] = ldg64_stream(px + j * 128); fv[j] = ldg64_stream(pf + j * 128); }
#pragma unroll
    for (int i = 0; i < 2; i++) {
        int k = threadIdx.x + i * TPB;
        if (k < 144) sgb[k] = gb[i];
    }
    __syncthreads();
    uint32_t a2 = a1 | (a1 << 16);
    uint32_t h[18];
    float s;
#pragma unroll
    for (int j = 0; j < 9; j++) { h[2*j+0] = hfma2(a2, xv[j].x, fv[j].x); h[2*j+1] = hfma2(a2, xv[j].y, fv[j].y); }
    float s0 = 0, s1 = 0, s2 = 0, s3 = 0;
#pragma unroll
    for (int i = 0; i < 18; i += 2) { s0 += lo(h[i]); s1 += hi(h[i]); s2 += lo(h[i+1]); s3 += hi(h[i+1]); }
    s = (s0 + s1) + (s2 + s3);
    s += __shfl_xor_sync(~0u, s, 1); s += __shfl_xor_sync(~0u, s, 2); s += __shfl_xor_sync(~0u, s, 4); s += __shfl_xor_sync(~0u, s, 8);
    float mean = s * (1.0f / 576.0f);
    s0 = s1 = s2 = s3 = 0;
#pragma unroll
    for (int i = 0; i < 18; i += 2) {
        float d0 = lo(h[i]) - mean, d1 = hi(h[i]) - mean, d2 = lo(h[i+1]) - mean, d3 = hi(h[i+1]) - mean;
        s0 = fmaf(d0, d0, s0); s1 = fmaf(d1, d1, s1); s2 = fmaf(d2, d2, s2); s3 = fmaf(d3, d3, s3);
    }
    s = (s0 + s1) + (s2 + s3);
    s += __shfl_xor_sync(~0u, s, 1); s += __shfl_xor_sync(~0u, s, 2); s += __shfl_xor_sync(~0u, s, 4); s += __shfl_xor_sync(~0u, s, 8);
    float var = rbf(s * (1.0f / 576.0f));
    float den = rbf(sqrtf(rbf(var + 1e-5f)));
    float rstd = __frcp_rn(den);
    float nm = -rbf(mean) * rstd;
    const uint2* sg = (const uint2*)sgb;
#pragma unroll
    for (int j = 0; j < 9; j++) {
        uint2 gv = sg[j * 16 + l], bv = sg[144 + j * 16 + l];
        uint2 o;
        o.x = hfma2(pack(fmaf(lo(h[2*j+0]), rstd, nm), fmaf(hi(h[2*j+0]), rstd, nm)), gv.x, bv.x);
        o.y = hfma2(pack(fmaf(lo(h[2*j+1]), rstd, nm), fmaf(hi(h[2*j+1]), rstd, nm)), gv.y, bv.y);
        stg64(po + j * 128, o);
    }
}

extern "C" void kernel_launch(void* const* d_in, const int* in_sizes, int n_in,
                              void* d_out, int out_size) {
    const bf16* x = (const bf16*)d_in[0];
    const bf16* f = (const bf16*)d_in[1];
    const bf16* g = (const bf16*)d_in[2];
    const bf16* b = (const bf16*)d_in[3];
    const bf16* alpha = (const bf16*)d_in[4];
    int rows = in_sizes[0] / 576;
    deepnorm_kernel<<<rows * 16 / TPB, TPB>>>(x, f, g, b, alpha, (bf16*)d_out);
}
```

```cpp
#include <cuda_runtime.h>
#include <cuda_bf16.h>
#include <stdint.h>

typedef __nv_bfloat16 bf16;

constexpr int D = 576;
constexpr int ROW_BYTES = D * 2;
constexpr int TPB = 128;
constexpr int ROWS_PER_CTA = TPB / 16;

__device__ __forceinline__ uint4 ldg128(const void* p) {
    uint4 v;
    asm volatile("ld.global.nc.v4.u32 {%0,%1,%2,%3}, [%4];"
                 : "=r"(v.x), "=r"(v.y), "=r"(v.z), "=r"(v.w) : "l"(p));
    return v;
}
__device__ __forceinline__ uint4 ldg128_stream(const void* p) {
    uint4 v;
    asm volatile("ld.global.nc.L1::no_allocate.v4.u32 {%0,%1,%2,%3}, [%4];"
                 : "=r"(v.x), "=r"(v.y), "=r"(v.z), "=r"(v.w) : "l"(p));
    return v;
}
__device__ __forceinline__ uint2 ldg64_stream(const void* p) {
    uint2 v;
    asm volatile("ld.global.nc.L1::no_allocate.v2.u32 {%0,%1}, [%2];" : "=r"(v.x), "=r"(v.y) : "l"(p));
    return v;
}
__device__ __forceinline__ void stg128(void* p, uint4 v) {
    asm volatile("st.global.v4.u32 [%0], {%1,%2,%3,%4};" :: "l"(p), "r"(v.x), "r"(v.y), "r"(v.z), "r"(v.w) : "memory");
}
__device__ __forceinline__ void stg64(void* p, uint2 v) {
    asm volatile("st.global.v2.u32 [%0], {%1,%2};" :: "l"(p), "r"(v.x), "r"(v.y) : "memory");
}
__device__ __forceinline__ uint4 lds128(uint32_t a) {
    uint4 v;
    asm volatile("ld.shared.v4.u32 {%0,%1,%2,%3}, [%4];" : "=r"(v.x), "=r"(v.y), "=r"(v.z), "=r"(v.w) : "r"(a) : "memory");
    return v;
}
__device__ __forceinline__ uint2 lds64(uint32_t a) {
    uint2 v;
    asm volatile("ld.shared.v2.u32 {%0,%1}, [%2];" : "=r"(v.x), "=r"(v.y) : "r"(a) : "memory");
    return v;
}
__device__ __forceinline__ uint32_t lds32(uint32_t a) {
    uint32_t v;
    asm volatile("ld.shared.u32 %0, [%1];" : "=r"(v) : "r"(a) : "memory");
    return v;
}
__device__ __forceinline__ void sts128(uint32_t a, uint4 v) {
    asm volatile("st.shared.v4.u32 [%0], {%1,%2,%3,%4};" :: "r"(a), "r"(v.x), "r"(v.y), "r"(v.z), "r"(v.w) : "memory");
}
__device__ __forceinline__ void sts32(uint32_t a, uint32_t v) {
    asm volatile("st.shared.u32 [%0], %1;" :: "r"(a), "r"(v) : "memory");
}
__device__ __forceinline__ uint32_t hfma2(uint32_t a, uint32_t b, uint32_t c) {
    uint32_t d; asm("fma.rn.bf16x2 %0, %1, %2, %3;" : "=r"(d) : "r"(a), "r"(b), "r"(c)); return d;
}
__device__ __forceinline__ uint32_t hmul2(uint32_t a, uint32_t b) {
    uint32_t d; asm("mul.rn.bf16x2 %0, %1, %2;" : "=r"(d) : "r"(a), "r"(b)); return d;
}
__device__ __forceinline__ uint32_t hadd2(uint32_t a, uint32_t b) {
    uint32_t d; asm("add.rn.bf16x2 %0, %1, %2;" : "=r"(d) : "r"(a), "r"(b)); return d;
}
__device__ __forceinline__ uint32_t hsub2(uint32_t a, uint32_t b) {
    uint32_t d; asm("sub.rn.bf16x2 %0, %1, %2;" : "=r"(d) : "r"(a), "r"(b)); return d;
}
__device__ __forceinline__ float lo_f32(uint32_t u) { return __uint_as_float(u << 16); }
__device__ __forceinline__ uint32_t dup_bf16(float v) {
    uint32_t d; asm("cvt.rn.bf16x2.f32 %0, %1, %1;" : "=r"(d) : "f"(v)); return d;
}
__device__ __forceinline__ float round_bf16(float v) {
    uint32_t d; asm("cvt.rn.bf16x2.f32 %0, %1, %2;" : "=r"(d) : "f"(v), "f"(0.f)); return __uint_as_float(d);
}
__device__ __forceinline__ float fast_sqrt(float v) { float d; asm("sqrt.approx.ftz.f32 %0, %1;" : "=f"(d) : "f"(v)); return d; }
__device__ __forceinline__ float fast_rcp(float v) { float d; asm("rcp.approx.ftz.f32 %0, %1;" : "=f"(d) : "f"(v)); return d; }

__device__ __forceinline__ void mma_sum_sumsq(float (&c)[4], uint32_t w) {
    const uint32_t ONES = 0x3F803F80u;
    asm("mma.sync.aligned.m16n8k8.row.col.f32.bf16.bf16.f32 {%0,%1,%2,%3}, {%4,%5}, {%4}, {%0,%1,%2,%3};"
        : "+f"(c[0]), "+f"(c[1]), "+f"(c[2]), "+f"(c[3]) : "r"(w), "r"(ONES));
}

template <bool GUARD>
__global__ void __launch_bounds__(TPB, 8)
deepnorm_kernel(const bf16* __restrict__ x, const bf16* __restrict__ f, const bf16* __restrict__ g,
                const bf16* __restrict__ b, const bf16* __restrict__ alpha, bf16* __restrict__ out,
                unsigned rows) {
    __shared__ uint4 sgb[145];
    const unsigned tid = threadIdx.x, lane = tid & 31, l = tid & 15;
    unsigned row = (blockIdx.x * TPB + tid) >> 4;
    const bool valid = !GUARD || row < rows;
    if (GUARD) row = min(row, rows - 1);
    const uint32_t sb = (uint32_t)__cvta_generic_to_shared(sgb);

    uint4 gq, bq; uint32_t a1;
    if (tid < 72) { gq = ldg128((const char*)g + tid * 16); bq = ldg128((const char*)b + tid * 16); }
    if (tid == TPB - 1) a1 = *(const unsigned short*)alpha;

    const char* px = (const char*)x + (size_t)row * ROW_BYTES;
    const char* pf = (const char*)f + (size_t)row * ROW_BYTES;
    uint32_t xw[18], fw[18];
#pragma unroll
    for (int j = 0; j < 4; j++) {
        uint4 v = ldg128_stream(px + j * 256 + l * 16);
        xw[4 * j] = v.x; xw[4 * j + 1] = v.y; xw[4 * j + 2] = v.z; xw[4 * j + 3] = v.w;
        v = ldg128_stream(pf + j * 256 + l * 16);
        fw[4 * j] = v.x; fw[4 * j + 1] = v.y; fw[4 * j + 2] = v.z; fw[4 * j + 3] = v.w;
    }
    {
        uint2 v = ldg64_stream(px + 1024 + l * 8); xw[16] = v.x; xw[17] = v.y;
        v = ldg64_stream(pf + 1024 + l * 8); fw[16] = v.x; fw[17] = v.y;
    }

    if (tid < 72) { sts128(sb + tid * 16, gq); sts128(sb + ROW_BYTES + tid * 16, bq); }
    if (tid == TPB - 1) sts32(sb + 2 * ROW_BYTES, a1 | (a1 << 16));
    __syncthreads();
    const uint32_t a2 = lds32(sb + 2 * ROW_BYTES);

    uint32_t h[18];
#pragma unroll
    for (int i = 0; i < 18; i++) h[i] = hfma2(a2, xw[i], fw[i]);

    const uint32_t k1 = __shfl_sync(~0u, h[0], lane & 16);
    const uint32_t k2 = __byte_perm(k1, 0, 0x1010);
    float c0[4] = {0, 0, 0, 0}, c1[4] = {0, 0, 0, 0}, c2[4] = {0, 0, 0, 0};
#pragma unroll
    for (int i = 0; i < 18; i += 3) {
        mma_sum_sumsq(c0, hsub2(h[i], k2));
        mma_sum_sumsq(c1, hsub2(h[i + 1], k2));
        mma_sum_sumsq(c2, hsub2(h[i + 2], k2));
    }
    const float w = (lane & 4) ? (c0[1] + c1[1] + c2[1]) : (c0[0] + c1[0] + c2[0]);
    const float u = (c0[2] + c1[2] + c2[2]) + (c0[3] + c1[3] + c2[3]);
    const int rb = lane & 16, tb = rb >> 3;
    const float s1 = __shfl_sync(~0u, u, tb) + __shfl_sync(~0u, u, tb + 1);
    const float s2 = (__shfl_sync(~0u, w, rb + tb) + __shfl_sync(~0u, w, rb + 4 + tb)) +
                     (__shfl_sync(~0u, w, rb + 8 + tb + 1) + __shfl_sync(~0u, w, rb + 12 + tb + 1));
    const float md = s1 * (1.0f / D);
    const float var = fmaxf(fmaf(-md, md, s2 * (1.0f / D)), 0.f);
    const uint32_t m2 = dup_bf16(md + lo_f32(k1));
    const float den = round_bf16(fast_sqrt(round_bf16(round_bf16(var) + 1e-5f)));
    const float rstd = fast_rcp(den);
    const uint32_t rh2 = dup_bf16(rstd);
    const uint32_t rl2 = dup_bf16(rstd - lo_f32(rh2));

    auto fin = [&](uint32_t hv, uint32_t gv, uint32_t bv) {
        const uint32_t dm = hsub2(hv, m2);
        const uint32_t q = hfma2(dm, rh2, hmul2(dm, rl2));
        return hadd2(hmul2(q, gv), bv);
    };
    char* po = (char*)out + (size_t)row * ROW_BYTES;
#pragma unroll
    for (int j = 0; j < 4; j++) {
        const int o = j * 256 + l * 16, i = 4 * j;
        const uint4 gv = lds128(sb + o), bv = lds128(sb + ROW_BYTES + o);
        const uint4 r = make_uint4(fin(h[i], gv.x, bv.x), fin(h[i + 1], gv.y, bv.y),
                                   fin(h[i + 2], gv.z, bv.z), fin(h[i + 3], gv.w, bv.w));
        if (valid) stg128(po + o, r);
    }
    {
        const int o = 1024 + l * 8;
        const uint2 gv = lds64(sb + o), bv = lds64(sb + ROW_BYTES + o);
        const uint2 r = make_uint2(fin(h[16], gv.x, bv.x), fin(h[17], gv.y, bv.y));
        if (valid) stg64(po + o, r);
    }
}

extern "C" void kernel_launch(void* const* d_in, const int* in_sizes, int n_in,
                              void* d_out, int out_size) {
    const bf16* x = (const bf16*)d_in[0];
    const bf16* f = (const bf16*)d_in[1];
    const bf16* g = (const bf16*)d_in[2];
    const bf16* b = (const bf16*)d_in[3];
    const bf16* alpha = (const bf16*)d_in[4];
    const unsigned rows = (unsigned)(in_sizes[0] / D);
    const unsigned grid = (rows + ROWS_PER_CTA - 1) / ROWS_PER_CTA;
    if (rows % ROWS_PER_CTA == 0)
        deepnorm_kernel<false><<<grid, TPB>>>(x, f, g, b, alpha, (bf16*)d_out, rows);
    else
        deepnorm_kernel<true><<<grid, TPB>>>(x, f, g, b, alpha, (bf16*)d_out, rows);
}
```

```cpp
#include <cuda_runtime.h>
#include <cuda_bf16.h>
#include <stdint.h>

typedef __nv_bfloat16 bf16;

constexpr int D = 576;
constexpr unsigned ROW_BYTES = D * 2;
constexpr int NWARP = 21;
constexpr int SLOT_CYCLES = 176;
constexpr int HEAD_CYCLES = 300;

__device__ __forceinline__ uint4 ldg128(const void* p) {
    uint4 v;
    asm volatile("ld.global.nc.v4.u32 {%0,%1,%2,%3}, [%4];"
                 : "=r"(v.x), "=r"(v.y), "=r"(v.z), "=r"(v.w) : "l"(p));
    return v;
}
__device__ __forceinline__ uint32_t ldg32(const void* p) {
    uint32_t v;
    asm volatile("ld.global.nc.u32 %0, [%1];" : "=r"(v) : "l"(p));
    return v;
}
__device__ __forceinline__ uint4 ldg128_stream(const void* p) {
    uint4 v;
    asm volatile("ld.global.nc.L1::no_allocate.v4.u32 {%0,%1,%2,%3}, [%4];"
                 : "=r"(v.x), "=r"(v.y), "=r"(v.z), "=r"(v.w) : "l"(p));
    return v;
}
__device__ __forceinline__ uint32_t ldg32_stream(const void* p) {
    uint32_t v;
    asm volatile("ld.global.nc.L1::no_allocate.u32 %0, [%1];" : "=r"(v) : "l"(p));
    return v;
}
__device__ __forceinline__ void stg128(void* p, uint4 v) {
    asm volatile("st.global.v4.u32 [%0], {%1,%2,%3,%4};" :: "l"(p), "r"(v.x), "r"(v.y), "r"(v.z), "r"(v.w) : "memory");
}
__device__ __forceinline__ void stg32(void* p, uint32_t v) {
    asm volatile("st.global.u32 [%0], %1;" :: "l"(p), "r"(v) : "memory");
}
__device__ __forceinline__ uint32_t hfma2(uint32_t a, uint32_t b, uint32_t c) {
    uint32_t d; asm("fma.rn.bf16x2 %0, %1, %2, %3;" : "=r"(d) : "r"(a), "r"(b), "r"(c)); return d;
}
__device__ __forceinline__ uint32_t hmul2(uint32_t a, uint32_t b) {
    uint32_t d; asm("mul.rn.bf16x2 %0, %1, %2;" : "=r"(d) : "r"(a), "r"(b)); return d;
}
__device__ __forceinline__ uint32_t hadd2(uint32_t a, uint32_t b) {
    uint32_t d; asm("add.rn.bf16x2 %0, %1, %2;" : "=r"(d) : "r"(a), "r"(b)); return d;
}
__device__ __forceinline__ uint32_t hsub2(uint32_t a, uint32_t b) {
    uint32_t d; asm("sub.rn.bf16x2 %0, %1, %2;" : "=r"(d) : "r"(a), "r"(b)); return d;
}
__device__ __forceinline__ float lo_f32(uint32_t u) { return __uint_as_float(u << 16); }
__device__ __forceinline__ float hi_f32(uint32_t u) { return __uint_as_float(u & 0xffff0000u); }
__device__ __forceinline__ uint32_t dup_bf16(float v) {
    uint32_t d; asm("cvt.rn.bf16x2.f32 %0, %1, %1;" : "=r"(d) : "f"(v)); return d;
}
__device__ __forceinline__ float round_bf16(float v) {
    uint32_t d; asm("cvt.rn.bf16x2.f32 %0, %1, %2;" : "=r"(d) : "f"(v), "f"(0.f)); return __uint_as_float(d);
}
__device__ __forceinline__ float fast_sqrt(float v) { float d; asm("sqrt.approx.ftz.f32 %0, %1;" : "=f"(d) : "f"(v)); return d; }
__device__ __forceinline__ float fast_rcp(float v) { float d; asm("rcp.approx.ftz.f32 %0, %1;" : "=f"(d) : "f"(v)); return d; }

__global__ void __launch_bounds__(NWARP * 32, 1)
deepnorm_kernel(const bf16* __restrict__ x, const bf16* __restrict__ f, const bf16* __restrict__ g,
                const bf16* __restrict__ b, const bf16* __restrict__ alpha, bf16* __restrict__ out,
                unsigned rows, unsigned G, int due_max) {
    const unsigned t0 = clock();
    const unsigned lane = threadIdx.x & 31, warp = threadIdx.x >> 5;
    unsigned row = warp * G + blockIdx.x;
    if (row >= rows) return;
    size_t off = (size_t)row * ROW_BYTES + lane * 16;
    const size_t step = (size_t)G * (NWARP * ROW_BYTES);
    const unsigned toff = 1024 - lane * 12;
    int due = (int)warp * SLOT_CYCLES - HEAD_CYCLES;

    uint32_t gw[9], bw[9], a2 = 0;
    bool first = true;
    do {
        const char* px = (const char*)x + off;
        const char* pf = (const char*)f + off;
        while ((int)(clock() - t0) < due) { }
        const uint4 x0 = ldg128_stream(px), f0 = ldg128_stream(pf);
        const uint4 x1 = ldg128_stream(px + 512), f1 = ldg128_stream(pf + 512);
        const uint32_t x2 = ldg32_stream(px + toff), f2 = ldg32_stream(pf + toff);
        if (first) {
            first = false;
#pragma unroll
            for (int j = 0; j < 2; j++) {
                uint4 v = ldg128((const char*)g + j * 512 + lane * 16);
                gw[4 * j] = v.x; gw[4 * j + 1] = v.y; gw[4 * j + 2] = v.z; gw[4 * j + 3] = v.w;
                v = ldg128((const char*)b + j * 512 + lane * 16);
                bw[4 * j] = v.x; bw[4 * j + 1] = v.y; bw[4 * j + 2] = v.z; bw[4 * j + 3] = v.w;
            }
            gw[8] = ldg32((const char*)g + 1024 + lane * 4);
            bw[8] = ldg32((const char*)b + 1024 + lane * 4);
            const uint32_t a1 = *(const unsigned short*)alpha;
            a2 = a1 | (a1 << 16);
        }
        char* po = (char*)out + off;
        row += NWARP * G; off += step; due = min(due + NWARP * SLOT_CYCLES, due_max);

        uint32_t h[9];
        h[0] = hfma2(a2, x0.x, f0.x); h[1] = hfma2(a2, x0.y, f0.y);
        h[2] = hfma2(a2, x0.z, f0.z); h[3] = hfma2(a2, x0.w, f0.w);
        h[4] = hfma2(a2, x1.x, f1.x); h[5] = hfma2(a2, x1.y, f1.y);
        h[6] = hfma2(a2, x1.z, f1.z); h[7] = hfma2(a2, x1.w, f1.w);
        h[8] = hfma2(a2, x2, f2);

        float a0 = lo_f32(h[0]), a1 = hi_f32(h[0]), q0 = a0 * a0, q1 = a1 * a1;
#pragma unroll
        for (int i = 1; i < 9; i++) {
            const float l = lo_f32(h[i]), u = hi_f32(h[i]);
            a0 += l; a1 += u; q0 = fmaf(l, l, q0); q1 = fmaf(u, u, q1);
        }
        float s1 = a0 + a1, s2 = q0 + q1;
#pragma unroll
        for (int m = 1; m < 32; m <<= 1) {
            s1 += __shfl_xor_sync(~0u, s1, m);
            s2 += __shfl_xor_sync(~0u, s2, m);
        }
        const float mean = s1 * (1.0f / D);
        const float ex2 = s2 * (1.0f / D);
        float var = fmaf(-mean, mean, ex2);
        if (__builtin_expect(!(var * 32.f >= ex2), 0)) {
            float r0 = 0.f, r1 = 0.f;
#pragma unroll
            for (int i = 0; i < 9; i++) {
                const float l = lo_f32(h[i]) - mean, u = hi_f32(h[i]) - mean;
                r0 = fmaf(l, l, r0); r1 = fmaf(u, u, r1);
            }
            float r = r0 + r1;
#pragma unroll
            for (int m = 1; m < 32; m <<= 1) r += __shfl_xor_sync(~0u, r, m);
            var = r * (1.0f / D);
        }
        const uint32_t m2 = dup_bf16(mean);
        const float den = round_bf16(fast_sqrt(round_bf16(round_bf16(var) + 1e-5f)));
        const float rstd = fast_rcp(den);
        const uint32_t rh2 = dup_bf16(rstd);
        const uint32_t rl2 = dup_bf16(rstd - lo_f32(rh2));
        auto fin = [&](int i) {
            const uint32_t dm = hsub2(h[i], m2);
            const uint32_t q = hfma2(dm, rh2, hmul2(dm, rl2));
            return hadd2(hmul2(q, gw[i]), bw[i]);
        };
        stg128(po, make_uint4(fin(0), fin(1), fin(2), fin(3)));
        stg128(po + 512, make_uint4(fin(4), fin(5), fin(6), fin(7)));
        stg32(po + toff, fin(8));
    } while (row < rows);
}

extern "C" void kernel_launch(void* const* d_in, const int* in_sizes, int n_in,
                              void* d_out, int out_size) {
    static int num_sms = 0;
    if (num_sms == 0) {
        int dev = 0;
        cudaGetDevice(&dev);
        cudaDeviceGetAttribute(&num_sms, cudaDevAttrMultiProcessorCount, dev);
        if (num_sms <= 0) num_sms = 132;
    }
    const unsigned rows = (unsigned)(in_sizes[0] / D);
    const unsigned G = (unsigned)num_sms;
    const int full_slots = (int)(rows / G);
    const int due_max = (full_slots > 0 ? full_slots - 1 : 0) * SLOT_CYCLES - HEAD_CYCLES;
    deepnorm_kernel<<<G, NWARP * 32>>>((const bf16*)d_in[0], (const bf16*)d_in[1], (const bf16*)d_in[2],
                                       (const bf16*)d_in[3], (const bf16*)d_in[4], (bf16*)d_out,
                                       rows, G, due_max);
}
```

```cpp
#include <cuda_runtime.h>
#include <cuda_bf16.h>
#include <stdint.h>
#include <type_traits>

typedef __nv_bfloat16 bf16;

constexpr int D = 576;
constexpr unsigned ROW_BYTES = D * 2;
constexpr int NWARP = 21;
constexpr int SLOT_CYCLES = 176;
constexpr int HEAD_CYCLES = 300;

__device__ __forceinline__ uint4 ldg128(const void* p) {
    uint4 v;
    asm volatile("ld.global.nc.v4.u32 {%0,%1,%2,%3}, [%4];"
                 : "=r"(v.x), "=r"(v.y), "=r"(v.z), "=r"(v.w) : "l"(p));
    return v;
}
__device__ __forceinline__ uint32_t ldg32(const void* p) {
    uint32_t v;
    asm volatile("ld.global.nc.u32 %0, [%1];" : "=r"(v) : "l"(p));
    return v;
}
__device__ __forceinline__ uint4 ldg128_stream(const void* p) {
    uint4 v;
    asm volatile("ld.global.nc.L1::no_allocate.v4.u32 {%0,%1,%2,%3}, [%4];"
                 : "=r"(v.x), "=r"(v.y), "=r"(v.z), "=r"(v.w) : "l"(p));
    return v;
}
__device__ __forceinline__ uint32_t ldg32_stream(const void* p) {
    uint32_t v;
    asm volatile("ld.global.nc.L1::no_allocate.u32 %0, [%1];" : "=r"(v) : "l"(p));
    return v;
}
__device__ __forceinline__ void stg128(void* p, uint4 v) {
    asm volatile("st.global.v4.u32 [%0], {%1,%2,%3,%4};" :: "l"(p), "r"(v.x), "r"(v.y), "r"(v.z), "r"(v.w) : "memory");
}
__device__ __forceinline__ void stg32(void* p, uint32_t v) {
    asm volatile("st.global.u32 [%0], %1;" :: "l"(p), "r"(v) : "memory");
}
__device__ __forceinline__ uint32_t hfma2(uint32_t a, uint32_t b, uint32_t c) {
    uint32_t d; asm("fma.rn.bf16x2 %0, %1, %2, %3;" : "=r"(d) : "r"(a), "r"(b), "r"(c)); return d;
}
__device__ __forceinline__ uint32_t hmul2(uint32_t a, uint32_t b) {
    uint32_t d; asm("mul.rn.bf16x2 %0, %1, %2;" : "=r"(d) : "r"(a), "r"(b)); return d;
}
__device__ __forceinline__ uint32_t hadd2(uint32_t a, uint32_t b) {
    uint32_t d; asm("add.rn.bf16x2 %0, %1, %2;" : "=r"(d) : "r"(a), "r"(b)); return d;
}
__device__ __forceinline__ uint32_t hsub2(uint32_t a, uint32_t b) {
    uint32_t d; asm("sub.rn.bf16x2 %0, %1, %2;" : "=r"(d) : "r"(a), "r"(b)); return d;
}
__device__ __forceinline__ float lo_f32(uint32_t u) { return __uint_as_float(u << 16); }
__device__ __forceinline__ float hi_f32(uint32_t u) { return __uint_as_float(u & 0xffff0000u); }
__device__ __forceinline__ uint32_t dup_bf16(float v) {
    uint32_t d; asm("cvt.rn.bf16x2.f32 %0, %1, %1;" : "=r"(d) : "f"(v)); return d;
}
__device__ __forceinline__ float round_bf16(float v) {
    uint32_t d; asm("cvt.rn.bf16x2.f32 %0, %1, %2;" : "=r"(d) : "f"(v), "f"(0.f)); return __uint_as_float(d);
}
__device__ __forceinline__ float fast_sqrt(float v) { float d; asm("sqrt.approx.ftz.f32 %0, %1;" : "=f"(d) : "f"(v)); return d; }
__device__ __forceinline__ float fast_rcp(float v) { float d; asm("rcp.approx.ftz.f32 %0, %1;" : "=f"(d) : "f"(v)); return d; }

template <unsigned CROWS, unsigned CG>
__global__ void __launch_bounds__(NWARP * 32, 1)
deepnorm_kernel(const bf16* __restrict__ x, const bf16* __restrict__ f, const bf16* __restrict__ g,
                const bf16* __restrict__ b, const bf16* __restrict__ alpha, bf16* __restrict__ out,
                unsigned rows_rt, unsigned G_rt) {
    typedef typename std::conditional<CROWS != 0, unsigned, size_t>::type off_t_;
    const unsigned t0 = clock();
    const unsigned rows = CROWS ? CROWS : rows_rt, G = CG ? CG : G_rt;
    const unsigned lane = threadIdx.x & 31, warp = threadIdx.x >> 5;
    unsigned row = warp * G + blockIdx.x;
    if ((CROWS == 0 || CROWS < NWARP * CG) && row >= rows) return;
    off_t_ off = (off_t_)row * ROW_BYTES + lane * 16;
    const off_t_ step = (off_t_)G * (NWARP * ROW_BYTES);
    const int due_max = (int)max(rows / G, 1u) * SLOT_CYCLES - SLOT_CYCLES - HEAD_CYCLES;
    const unsigned toff = 1024 - lane * 12;
    int due = (int)warp * SLOT_CYCLES - HEAD_CYCLES;

    uint32_t gw[9], bw[9], a2 = 0;
    bool first = true;
    do {
        const char* px = (const char*)x + off;
        const char* pf = (const char*)f + off;
        while ((int)(clock() - t0) < due) { }
        const uint4 x0 = ldg128_stream(px), f0 = ldg128_stream(pf);
        const uint4 x1 = ldg128_stream(px + 512), f1 = ldg128_stream(pf + 512);
        const uint32_t x2 = ldg32_stream(px + toff), f2 = ldg32_stream(pf + toff);
        if (first) {
            first = false;
#pragma unroll
            for (int j = 0; j < 2; j++) {
                uint4 v = ldg128((const char*)g + j * 512 + lane * 16);
                gw[4 * j] = v.x; gw[4 * j + 1] = v.y; gw[4 * j + 2] = v.z; gw[4 * j + 3] = v.w;
                v = ldg128((const char*)b + j * 512 + lane * 16);
                bw[4 * j] = v.x; bw[4 * j + 1] = v.y; bw[4 * j + 2] = v.z; bw[4 * j + 3] = v.w;
            }
            gw[8] = ldg32((const char*)g + 1024 + lane * 4);
            bw[8] = ldg32((const char*)b + 1024 + lane * 4);
            const uint32_t a1 = *(const unsigned short*)alpha;
            a2 = a1 | (a1 << 16);
        }
        char* po = (char*)out + off;
        row += NWARP * G; off += step; due = min(due + NWARP * SLOT_CYCLES, due_max);

        uint32_t h[9];
        h[0] = hfma2(a2, x0.x, f0.x); h[1] = hfma2(a2, x0.y, f0.y);
        h[2] = hfma2(a2, x0.z, f0.z); h[3] = hfma2(a2, x0.w, f0.w);
        h[4] = hfma2(a2, x1.x, f1.x); h[5] = hfma2(a2, x1.y, f1.y);
        h[6] = hfma2(a2, x1.z, f1.z); h[7] = hfma2(a2, x1.w, f1.w);
        h[8] = hfma2(a2, x2, f2);

        float a0 = lo_f32(h[0]), a1 = hi_f32(h[0]), q0 = a0 * a0, q1 = a1 * a1;
#pragma unroll
        for (int i = 1; i < 9; i++) {
            const float l = lo_f32(h[i]), u = hi_f32(h[i]);
            a0 += l; a1 += u; q0 = fmaf(l, l, q0); q1 = fmaf(u, u, q1);
        }
        float s1 = a0 + a1, s2 = q0 + q1;
#pragma unroll
        for (int m = 1; m < 32; m <<= 1) {
            s1 += __shfl_xor_sync(~0u, s1, m);
            s2 += __shfl_xor_sync(~0u, s2, m);
        }
        const float mean = s1 * (1.0f / D);
        const float ex2 = s2 * (1.0f / D);
        float var = fmaf(-mean, mean, ex2);
        if (__builtin_expect(!(var * 32.f >= ex2), 0)) {
            float r0 = 0.f, r1 = 0.f;
#pragma unroll
            for (int i = 0; i < 9; i++) {
                const float l = lo_f32(h[i]) - mean, u = hi_f32(h[i]) - mean;
                r0 = fmaf(l, l, r0); r1 = fmaf(u, u, r1);
            }
            float r = r0 + r1;
#pragma unroll
            for (int m = 1; m < 32; m <<= 1) r += __shfl_xor_sync(~0u, r, m);
            var = r * (1.0f / D);
        }
        const uint32_t m2 = dup_bf16(mean);
        const float den = round_bf16(fast_sqrt(round_bf16(round_bf16(var) + 1e-5f)));
        const float rstd = fast_rcp(den);
        const uint32_t rh2 = dup_bf16(rstd);
        const uint32_t rl2 = dup_bf16(rstd - lo_f32(rh2));
        auto fin = [&](int i) {
            const uint32_t dm = hsub2(h[i], m2);
            const uint32_t q = hfma2(dm, rh2, hmul2(dm, rl2));
            return hadd2(hmul2(q, gw[i]), bw[i]);
        };
        stg128(po, make_uint4(fin(0), fin(1), fin(2), fin(3)));
        stg128(po + 512, make_uint4(fin(4), fin(5), fin(6), fin(7)));
        stg32(po + toff, fin(8));
    } while (row < rows);
}

extern "C" void kernel_launch(void* const* d_in, const int* in_sizes, int n_in,
                              void* d_out, int out_size) {
    static int num_sms = 0;
    if (num_sms == 0) {
        int dev = 0;
        cudaGetDevice(&dev);
        cudaDeviceGetAttribute(&num_sms, cudaDevAttrMultiProcessorCount, dev);
        if (num_sms <= 0) num_sms = 132;
    }
    const unsigned rows = (unsigned)(in_sizes[0] / D);
    const unsigned G = (unsigned)num_sms;
    auto kern = (rows == 8192 && G == 132) ? deepnorm_kernel<8192, 132> : deepnorm_kernel<0, 0>;
    kern<<<G, NWARP * 32>>>((const bf16*)d_in[0], (const bf16*)d_in[1], (const bf16*)d_in[2],
                            (const bf16*)d_in[3], (const bf16*)d_in[4], (bf16*)d_out, rows, G);
}
```

```cpp
#include <cuda_runtime.h>
#include <cuda_bf16.h>
#include <stdint.h>

typedef __nv_bfloat16 bf16;

constexpr int D = 576;
constexpr unsigned ROW_VEC = D * 2 / 16;
constexpr int NWARP = 21;
constexpr int SLOT_CYCLES = 176;
constexpr int HEAD_CYCLES = 300;

__device__ __forceinline__ uint4 ldg128(const void* p) {
    uint4 v;
    asm volatile("ld.global.nc.v4.u32 {%0,%1,%2,%3}, [%4];"
                 : "=r"(v.x), "=r"(v.y), "=r"(v.z), "=r"(v.w) : "l"(p));
    return v;
}
__device__ __forceinline__ uint32_t ldg32(const void* p) {
    uint32_t v;
    asm volatile("ld.global.nc.u32 %0, [%1];" : "=r"(v) : "l"(p));
    return v;
}
__device__ __forceinline__ uint4 ldg128_stream(const void* p) {
    uint4 v;
    asm volatile("ld.global.nc.L1::no_allocate.v4.u32 {%0,%1,%2,%3}, [%4];"
                 : "=r"(v.x), "=r"(v.y), "=r"(v.z), "=r"(v.w) : "l"(p));
    return v;
}
__device__ __forceinline__ uint32_t ldg32_stream(const void* p) {
    uint32_t v;
    asm volatile("ld.global.nc.L1::no_allocate.u32 %0, [%1];" : "=r"(v) : "l"(p));
    return v;
}
__device__ __forceinline__ void stg128(void* p, uint4 v) {
    asm volatile("st.global.v4.u32 [%0], {%1,%2,%3,%4};" :: "l"(p), "r"(v.x), "r"(v.y), "r"(v.z), "r"(v.w) : "memory");
}
__device__ __forceinline__ void stg32(void* p, uint32_t v) {
    asm volatile("st.global.u32 [%0], %1;" :: "l"(p), "r"(v) : "memory");
}
__device__ __forceinline__ uint32_t hfma2(uint32_t a, uint32_t b, uint32_t c) {
    uint32_t d; asm("fma.rn.bf16x2 %0, %1, %2, %3;" : "=r"(d) : "r"(a), "r"(b), "r"(c)); return d;
}
__device__ __forceinline__ uint32_t hmul2(uint32_t a, uint32_t b) {
    uint32_t d; asm("mul.rn.bf16x2 %0, %1, %2;" : "=r"(d) : "r"(a), "r"(b)); return d;
}
__device__ __forceinline__ uint32_t hadd2(uint32_t a, uint32_t b) {
    uint32_t d; asm("add.rn.bf16x2 %0, %1, %2;" : "=r"(d) : "r"(a), "r"(b)); return d;
}
__device__ __forceinline__ uint32_t hsub2(uint32_t a, uint32_t b) {
    uint32_t d; asm("sub.rn.bf16x2 %0, %1, %2;" : "=r"(d) : "r"(a), "r"(b)); return d;
}
__device__ __forceinline__ float lo_f32(uint32_t u) { return __uint_as_float(u << 16); }
__device__ __forceinline__ float hi_f32(uint32_t u) { return __uint_as_float(u & 0xffff0000u); }
__device__ __forceinline__ uint32_t dup_bf16(float v) {
    uint32_t d; asm("cvt.rn.bf16x2.f32 %0, %1, %1;" : "=r"(d) : "f"(v)); return d;
}
__device__ __forceinline__ float round_bf16(float v) {
    uint32_t d; asm("cvt.rn.bf16x2.f32 %0, %1, %2;" : "=r"(d) : "f"(v), "f"(0.f)); return __uint_as_float(d);
}
__device__ __forceinline__ float fast_sqrt(float v) { float d; asm("sqrt.approx.ftz.f32 %0, %1;" : "=f"(d) : "f"(v)); return d; }
__device__ __forceinline__ float fast_rcp(float v) { float d; asm("rcp.approx.ftz.f32 %0, %1;" : "=f"(d) : "f"(v)); return d; }

template <unsigned CROWS, unsigned CG>
__global__ void __launch_bounds__(NWARP * 32, 1)
deepnorm_kernel(const bf16* __restrict__ x, const bf16* __restrict__ f, const bf16* __restrict__ g,
                const bf16* __restrict__ b, const bf16* __restrict__ alpha, bf16* __restrict__ out,
                unsigned rows_rt, unsigned G_rt) {
    const unsigned rows = CROWS ? CROWS : rows_rt, G = CG ? CG : G_rt;
    const unsigned lane = threadIdx.x & 31, warp = threadIdx.x >> 5;
    unsigned row = warp * G + blockIdx.x;
    const unsigned idx = row * ROW_VEC + lane;
    const char* px = (const char*)((const uint4*)x + idx);
    const char* pf = (const char*)((const uint4*)f + idx);
    const unsigned t0 = clock();
    const size_t step = (size_t)G * (NWARP * ROW_VEC * 16);
    const unsigned toff = 1024 - lane * 12;
    int due = (int)warp * SLOT_CYCLES - HEAD_CYCLES;
    const int due_max = (int)max(rows / G, 1u) * SLOT_CYCLES - SLOT_CYCLES - HEAD_CYCLES;
    if (px == nullptr || pf == nullptr) return;
    if ((CROWS == 0 || CROWS < NWARP * CG) && row >= rows) return;

    if (due > 0) while ((int)(clock() - t0) < due) { }
    uint4 x0 = ldg128_stream(px), f0 = ldg128_stream(pf);
    uint4 x1 = ldg128_stream(px + 512), f1 = ldg128_stream(pf + 512);
    uint32_t x2 = ldg32_stream(px + toff), f2 = ldg32_stream(pf + toff);

    uint32_t gw[9], bw[9];
#pragma unroll
    for (int j = 0; j < 2; j++) {
        uint4 v = ldg128((const char*)g + j * 512 + lane * 16);
        gw[4 * j] = v.x; gw[4 * j + 1] = v.y; gw[4 * j + 2] = v.z; gw[4 * j + 3] = v.w;
        v = ldg128((const char*)b + j * 512 + lane * 16);
        bw[4 * j] = v.x; bw[4 * j + 1] = v.y; bw[4 * j + 2] = v.z; bw[4 * j + 3] = v.w;
    }
    gw[8] = ldg32((const char*)g + 1024 + lane * 4);
    bw[8] = ldg32((const char*)b + 1024 + lane * 4);
    const uint32_t a1 = *(const unsigned short*)alpha;
    const uint32_t a2 = a1 | (a1 << 16);
    char* po = (char*)out + (px - (const char*)x);

    while (true) {
        __syncwarp();
        uint32_t h[9];
        h[0] = hfma2(a2, x0.x, f0.x); h[1] = hfma2(a2, x0.y, f0.y);
        h[2] = hfma2(a2, x0.z, f0.z); h[3] = hfma2(a2, x0.w, f0.w);
        h[4] = hfma2(a2, x1.x, f1.x); h[5] = hfma2(a2, x1.y, f1.y);
        h[6] = hfma2(a2, x1.z, f1.z); h[7] = hfma2(a2, x1.w, f1.w);
        h[8] = hfma2(a2, x2, f2);

        float a0 = lo_f32(h[0]), a3 = hi_f32(h[0]), q0 = a0 * a0, q1 = a3 * a3;
#pragma unroll
        for (int i = 1; i < 9; i++) {
            const float l = lo_f32(h[i]), u = hi_f32(h[i]);
            a0 += l; a3 += u; q0 = fmaf(l, l, q0); q1 = fmaf(u, u, q1);
        }
        float s1 = a0 + a3, s2 = q0 + q1;
#pragma unroll
        for (int m = 1; m < 32; m <<= 1) {
            s1 += __shfl_xor_sync(~0u, s1, m);
            s2 += __shfl_xor_sync(~0u, s2, m);
        }
        const float mean = s1 * (1.0f / D);
        const float ex2 = s2 * (1.0f / D);
        const float var = fmaf(-mean, mean, ex2);
        const uint32_t m2 = dup_bf16(mean);

        auto emit = [&](float v) {
            const float den = round_bf16(fast_sqrt(round_bf16(round_bf16(v) + 1e-5f)));
            const float rstd = fast_rcp(den);
            const uint32_t rh2 = dup_bf16(rstd);
            const uint32_t rl2 = dup_bf16(rstd - lo_f32(rh2));
            auto fin = [&](int i) {
                const uint32_t dm = hsub2(h[i], m2);
                const uint32_t q = hfma2(dm, rh2, hmul2(dm, rl2));
                return hadd2(hmul2(q, gw[i]), bw[i]);
            };
            stg128(po, make_uint4(fin(0), fin(1), fin(2), fin(3)));
            stg128(po + 512, make_uint4(fin(4), fin(5), fin(6), fin(7)));
            stg32(po + toff, fin(8));
        };
        emit(var);
        if (__builtin_expect(!(var * 32.f >= ex2), 0)) {
            float r0 = 0.f, r1 = 0.f;
#pragma unroll
            for (int i = 0; i < 9; i++) {
                const float l = lo_f32(h[i]) - mean, u = hi_f32(h[i]) - mean;
                r0 = fmaf(l, l, r0); r1 = fmaf(u, u, r1);
            }
            float r = r0 + r1;
#pragma unroll
            for (int m = 1; m < 32; m <<= 1) r += __shfl_xor_sync(~0u, r, m);
            emit(r * (1.0f / D));
        }

        row += NWARP * G;
        if (row >= rows) break;
        px += step; pf += step; po += step;
        due = min(due + NWARP * SLOT_CYCLES, due_max);
        while ((int)(clock() - t0) < due) { }
        x0 = ldg128_stream(px); f0 = ldg128_stream(pf);
        x1 = ldg128_stream(px + 512); f1 = ldg128_stream(pf + 512);
        x2 = ldg32_stream(px + toff); f2 = ldg32_stream(pf + toff);
    }
}

extern "C" void kernel_launch(void* const* d_in, const int* in_sizes, int n_in,
                              void* d_out, int out_size) {
    static int num_sms = 0;
    if (num_sms == 0) {
        int dev = 0;
        cudaGetDevice(&dev);
        cudaDeviceGetAttribute(&num_sms, cudaDevAttrMultiProcessorCount, dev);
        if (num_sms <= 0) num_sms = 132;
    }
    const unsigned rows = (unsigned)(in_sizes[0] / D);
    const unsigned G = (unsigned)num_sms;
    auto kern = (rows == 8192 && G == 132) ? deepnorm_kernel<8192, 132> : deepnorm_kernel<0, 0>;
    kern<<<G, NWARP * 32>>>((const bf16*)d_in[0], (const bf16*)d_in[1], (const bf16*)d_in[2],
                            (const bf16*)d_in[3], (const bf16*)d_in[4], (bf16*)d_out, rows, G);
}
```

```cpp
#include <cuda_runtime.h>
#include <cuda_bf16.h>
#include <stdint.h>

typedef __nv_bfloat16 bf16;

constexpr int D = 576;
constexpr unsigned ROW_VEC = D * 2 / 16;
constexpr int NWARP = 21;
constexpr int SLOT_CYCLES = 176;
constexpr int HEAD_CYCLES = 300;

__device__ __forceinline__ uint4 ldg128(const void* p) {
    uint4 v;
    asm volatile("ld.global.nc.v4.u32 {%0,%1,%2,%3}, [%4];"
                 : "=r"(v.x), "=r"(v.y), "=r"(v.z), "=r"(v.w) : "l"(p));
    return v;
}
__device__ __forceinline__ uint32_t ldg32(const void* p) {
    uint32_t v;
    asm volatile("ld.global.nc.u32 %0, [%1];" : "=r"(v) : "l"(p));
    return v;
}
__device__ __forceinline__ uint4 ldg128_stream(const void* p) {
    uint4 v;
    asm volatile("ld.global.nc.L1::no_allocate.v4.u32 {%0,%1,%2,%3}, [%4];"
                 : "=r"(v.x), "=r"(v.y), "=r"(v.z), "=r"(v.w) : "l"(p));
    return v;
}
__device__ __forceinline__ uint32_t ldg32_stream(const void* p) {
    uint32_t v;
    asm volatile("ld.global.nc.L1::no_allocate.u32 %0, [%1];" : "=r"(v) : "l"(p));
    return v;
}
__device__ __forceinline__ void stg128(void* p, uint4 v) {
    asm volatile("st.global.v4.u32 [%0], {%1,%2,%3,%4};" :: "l"(p), "r"(v.x), "r"(v.y), "r"(v.z), "r"(v.w) : "memory");
}
__device__ __forceinline__ void stg32(void* p, uint32_t v) {
    asm volatile("st.global.u32 [%0], %1;" :: "l"(p), "r"(v) : "memory");
}
__device__ __forceinline__ uint32_t hfma2(uint32_t a, uint32_t b, uint32_t c) {
    uint32_t d; asm("fma.rn.bf16x2 %0, %1, %2, %3;" : "=r"(d) : "r"(a), "r"(b), "r"(c)); return d;
}
__device__ __forceinline__ uint32_t hmul2(uint32_t a, uint32_t b) {
    uint32_t d; asm("mul.rn.bf16x2 %0, %1, %2;" : "=r"(d) : "r"(a), "r"(b)); return d;
}
__device__ __forceinline__ uint32_t hadd2(uint32_t a, uint32_t b) {
    uint32_t d; asm("add.rn.bf16x2 %0, %1, %2;" : "=r"(d) : "r"(a), "r"(b)); return d;
}
__device__ __forceinline__ uint32_t hsub2(uint32_t a, uint32_t b) {
    uint32_t d; asm("sub.rn.bf16x2 %0, %1, %2;" : "=r"(d) : "r"(a), "r"(b)); return d;
}
__device__ __forceinline__ float lo_f32(uint32_t u) { return __uint_as_float(u << 16); }
__device__ __forceinline__ float hi_f32(uint32_t u) { return __uint_as_float(u & 0xffff0000u); }
__device__ __forceinline__ uint32_t dup_bf16(float v) {
    uint32_t d; asm("cvt.rn.bf16x2.f32 %0, %1, %1;" : "=r"(d) : "f"(v)); return d;
}
__device__ __forceinline__ float round_bf16(float v) {
    uint32_t d; asm("cvt.rn.bf16x2.f32 %0, %1, %2;" : "=r"(d) : "f"(v), "f"(0.f)); return __uint_as_float(d);
}
__device__ __forceinline__ float fast_sqrt(float v) { float d; asm("sqrt.approx.ftz.f32 %0, %1;" : "=f"(d) : "f"(v)); return d; }
__device__ __forceinline__ float fast_rcp(float v) { float d; asm("rcp.approx.ftz.f32 %0, %1;" : "=f"(d) : "f"(v)); return d; }

template <unsigned CROWS, unsigned CG>
__global__ void __launch_bounds__(NWARP * 32, 1)
deepnorm_kernel(const bf16* __restrict__ x, const bf16* __restrict__ f, const bf16* __restrict__ g,
                const bf16* __restrict__ b, const bf16* __restrict__ alpha, bf16* __restrict__ out,
                unsigned rows_rt, unsigned G_rt) {
    const unsigned rows = CROWS ? CROWS : rows_rt, G = CG ? CG : G_rt;
    const unsigned lane = threadIdx.x & 31, warp = threadIdx.x >> 5;
    unsigned row = warp * G + blockIdx.x;
    const unsigned idx = row * ROW_VEC + lane;
    const char* px = (const char*)((const uint4*)x + idx);
    const char* pf = (const char*)((const uint4*)f + idx);
    const unsigned t0 = clock();
    const size_t step = (size_t)G * (NWARP * ROW_VEC * 16);
    const unsigned toff = 1024 - lane * 12;
    int due = (int)warp * SLOT_CYCLES - HEAD_CYCLES;
    const int due_max = (int)max(rows / G, 1u) * SLOT_CYCLES - SLOT_CYCLES - HEAD_CYCLES;
    if (px == nullptr || pf == nullptr) return;
    if ((CROWS == 0 || CROWS < NWARP * CG) && row >= rows) return;

    if (due > 0) while ((int)(clock() - t0) < due) { }
    uint4 x0 = ldg128_stream(px), f0 = ldg128_stream(pf);
    uint4 x1 = ldg128_stream(px + 512), f1 = ldg128_stream(pf + 512);
    uint32_t x2 = ldg32_stream(px + toff), f2 = ldg32_stream(pf + toff);

    uint32_t gw[9], bw[9];
#pragma unroll
    for (int j = 0; j < 2; j++) {
        uint4 v = ldg128((const char*)g + j * 512 + lane * 16);
        gw[4 * j] = v.x; gw[4 * j + 1] = v.y; gw[4 * j + 2] = v.z; gw[4 * j + 3] = v.w;
        v = ldg128((const char*)b + j * 512 + lane * 16);
        bw[4 * j] = v.x; bw[4 * j + 1] = v.y; bw[4 * j + 2] = v.z; bw[4 * j + 3] = v.w;
    }
    gw[8] = ldg32((const char*)g + 1024 + lane * 4);
    bw[8] = ldg32((const char*)b + 1024 + lane * 4);
    const uint32_t a1 = *(const unsigned short*)alpha;
    const uint32_t a2 = a1 | (a1 << 16);
    char* po = (char*)out + (px - (const char*)x);

    while (true) {
        __syncwarp();
        auto axf = [&](uint32_t xv, uint32_t fv) { return hadd2(hmul2(a2, xv), fv); };
        uint32_t h[9];
        h[0] = axf(x0.x, f0.x); h[1] = axf(x0.y, f0.y); h[2] = axf(x0.z, f0.z); h[3] = axf(x0.w, f0.w);
        h[4] = axf(x1.x, f1.x); h[5] = axf(x1.y, f1.y); h[6] = axf(x1.z, f1.z); h[7] = axf(x1.w, f1.w);
        h[8] = axf(x2, f2);

        float a0 = lo_f32(h[0]), a3 = hi_f32(h[0]), q0 = a0 * a0, q1 = a3 * a3;
#pragma unroll
        for (int i = 1; i < 9; i++) {
            const float l = lo_f32(h[i]), u = hi_f32(h[i]);
            a0 += l; a3 += u; q0 = fmaf(l, l, q0); q1 = fmaf(u, u, q1);
        }
        float s1 = a0 + a3, s2 = q0 + q1;
#pragma unroll
        for (int m = 1; m < 32; m <<= 1) {
            s1 += __shfl_xor_sync(~0u, s1, m);
            s2 += __shfl_xor_sync(~0u, s2, m);
        }
        const float mean = s1 * (1.0f / D);
        const float ex2 = s2 * (1.0f / D);
        const float var = fmaf(-mean, mean, ex2);
        const uint32_t m2 = dup_bf16(mean);

        auto emit = [&](float v) {
            const float den = round_bf16(fast_sqrt(round_bf16(round_bf16(v) + 1e-5f)));
            const float rstd = fast_rcp(den);
            const uint32_t rh2 = dup_bf16(rstd);
            const uint32_t rl2 = dup_bf16(rstd - lo_f32(rh2));
            auto fin = [&](int i) {
                const uint32_t dm = hsub2(h[i], m2);
                const uint32_t q = hfma2(dm, rh2, hmul2(dm, rl2));
                return hadd2(hmul2(q, gw[i]), bw[i]);
            };
            stg128(po, make_uint4(fin(0), fin(1), fin(2), fin(3)));
            stg128(po + 512, make_uint4(fin(4), fin(5), fin(6), fin(7)));
            stg32(po + toff, fin(8));
        };
        emit(var);
        if (__builtin_expect(!(var * 32.f >= ex2), 0)) {
            float r0 = 0.f, r1 = 0.f;
#pragma unroll
            for (int i = 0; i < 9; i++) {
                const float l = lo_f32(h[i]) - mean, u = hi_f32(h[i]) - mean;
                r0 = fmaf(l, l, r0); r1 = fmaf(u, u, r1);
            }
            float r = r0 + r1;
#pragma unroll
            for (int m = 1; m < 32; m <<= 1) r += __shfl_xor_sync(~0u, r, m);
            emit(r * (1.0f / D));
        }

        row += NWARP * G;
        if (row >= rows) break;
        px += step; pf += step; po += step;
        due = min(due + NWARP * SLOT_CYCLES, due_max);
        while ((int)(clock() - t0) < due) { }
        x0 = ldg128_stream(px); f0 = ldg128_stream(pf);
        x1 = ldg128_stream(px + 512); f1 = ldg128_stream(pf + 512);
        x2 = ldg32_stream(px + toff); f2 = ldg32_stream(pf + toff);
    }
}

extern "C" void kernel_launch(void* const* d_in, const int* in_sizes, int n_in,
                              void* d_out, int out_size) {
    static int num_sms = 0;
    if (num_sms == 0) {
        int dev = 0;
        cudaGetDevice(&dev);
        cudaDeviceGetAttribute(&num_sms, cudaDevAttrMultiProcessorCount, dev);
        if (num_sms <= 0) num_sms = 132;
    }
    const unsigned rows = (unsigned)(in_sizes[0] / D);
    const unsigned G = (unsigned)num_sms;
    auto kern = (rows == 8192 && G == 132) ? deepnorm_kernel<8192, 132> : deepnorm_kernel<0, 0>;
    kern<<<G, NWARP * 32>>>((const bf16*)d_in[0], (const bf16*)d_in[1], (const bf16*)d_in[2],
                            (const bf16*)d_in[3], (const bf16*)d_in[4], (bf16*)d_out, rows, G);
}
```

```cpp
#include <cuda_runtime.h>
#include <cuda_bf16.h>
#include <stdint.h>

typedef __nv_bfloat16 bf16;

constexpr int D = 576;
constexpr unsigned ROW_VEC = D * 2 / 16;
constexpr int NWARP = 18;
constexpr int SLOT_CYCLES = 188;
constexpr int HEAD_CYCLES = 400;

__device__ __forceinline__ uint4 ldg128(const void* p) {
    uint4 v;
    asm volatile("ld.global.nc.v4.u32 {%0,%1,%2,%3}, [%4];"
                 : "=r"(v.x), "=r"(v.y), "=r"(v.z), "=r"(v.w) : "l"(p));
    return v;
}
__device__ __forceinline__ uint32_t ldg32(const void* p) {
    uint32_t v;
    asm volatile("ld.global.nc.u32 %0, [%1];" : "=r"(v) : "l"(p));
    return v;
}
__device__ __forceinline__ uint4 ldg128_stream(const void* p) {
    uint4 v;
    asm volatile("ld.global.nc.L1::no_allocate.v4.u32 {%0,%1,%2,%3}, [%4];"
                 : "=r"(v.x), "=r"(v.y), "=r"(v.z), "=r"(v.w) : "l"(p));
    return v;
}
__device__ __forceinline__ uint32_t ldg32_stream(const void* p) {
    uint32_t v;
    asm volatile("ld.global.nc.L1::no_allocate.u32 %0, [%1];" : "=r"(v) : "l"(p));
    return v;
}
__device__ __forceinline__ void stg128(void* p, uint4 v) {
    asm volatile("st.global.v4.u32 [%0], {%1,%2,%3,%4};" :: "l"(p), "r"(v.x), "r"(v.y), "r"(v.z), "r"(v.w) : "memory");
}
__device__ __forceinline__ void stg32(void* p, uint32_t v) {
    asm volatile("st.global.u32 [%0], %1;" :: "l"(p), "r"(v) : "memory");
}
__device__ __forceinline__ uint32_t hfma2(uint32_t a, uint32_t b, uint32_t c) {
    uint32_t d; asm("fma.rn.bf16x2 %0, %1, %2, %3;" : "=r"(d) : "r"(a), "r"(b), "r"(c)); return d;
}
__device__ __forceinline__ uint32_t hmul2(uint32_t a, uint32_t b) {
    uint32_t d; asm("mul.rn.bf16x2 %0, %1, %2;" : "=r"(d) : "r"(a), "r"(b)); return d;
}
__device__ __forceinline__ uint32_t hadd2(uint32_t a, uint32_t b) {
    uint32_t d; asm("add.rn.bf16x2 %0, %1, %2;" : "=r"(d) : "r"(a), "r"(b)); return d;
}
__device__ __forceinline__ uint32_t hsub2(uint32_t a, uint32_t b) {
    uint32_t d; asm("sub.rn.bf16x2 %0, %1, %2;" : "=r"(d) : "r"(a), "r"(b)); return d;
}
__device__ __forceinline__ float lo_f32(uint32_t u) { return __uint_as_float(u << 16); }
__device__ __forceinline__ float hi_f32(uint32_t u) { return __uint_as_float(u & 0xffff0000u); }
__device__ __forceinline__ uint32_t dup_bf16(float v) {
    uint32_t d; asm("cvt.rn.bf16x2.f32 %0, %1, %1;" : "=r"(d) : "f"(v)); return d;
}
__device__ __forceinline__ float round_bf16(float v) {
    uint32_t d; asm("cvt.rn.bf16x2.f32 %0, %1, %2;" : "=r"(d) : "f"(v), "f"(0.f)); return __uint_as_float(d);
}
__device__ __forceinline__ float fast_sqrt(float v) { float d; asm("sqrt.approx.ftz.f32 %0, %1;" : "=f"(d) : "f"(v)); return d; }
__device__ __forceinline__ float fast_rcp(float v) { float d; asm("rcp.approx.ftz.f32 %0, %1;" : "=f"(d) : "f"(v)); return d; }

template <unsigned CROWS, unsigned CG>
__global__ void __launch_bounds__(NWARP * 32, 1)
deepnorm_kernel(const bf16* __restrict__ x, const bf16* __restrict__ f, const bf16* __restrict__ g,
                const bf16* __restrict__ b, const bf16* __restrict__ alpha, bf16* __restrict__ out,
                unsigned rows_rt, unsigned G_rt) {
    const unsigned rows = CROWS ? CROWS : rows_rt, G = CG ? CG : G_rt;
    const unsigned lane = threadIdx.x & 31, warp = threadIdx.x >> 5;
    unsigned row = warp * G + blockIdx.x;
    const unsigned idx = row * ROW_VEC + lane;
    const char* px = (const char*)((const uint4*)x + idx);
    const char* pf = (const char*)((const uint4*)f + idx);
    const unsigned t0 = clock();
    const size_t step = (size_t)G * (NWARP * ROW_VEC * 16);
    const unsigned toff = 1024 - lane * 12;
    int due = (int)warp * SLOT_CYCLES - HEAD_CYCLES;
    const int due_max = (int)max(rows / G, 1u) * SLOT_CYCLES - SLOT_CYCLES - HEAD_CYCLES;
    if (px == nullptr || pf == nullptr) return;
    if ((CROWS == 0 || CROWS < NWARP * CG) && row >= rows) return;

    if (due > 0) while ((int)(clock() - t0) < due) { }
    uint4 x0 = ldg128_stream(px), f0 = ldg128_stream(pf);
    uint4 x1 = ldg128_stream(px + 512), f1 = ldg128_stream(pf + 512);
    uint32_t x2 = ldg32_stream(px + toff), f2 = ldg32_stream(pf + toff);

    uint32_t gw[9], bw[9];
#pragma unroll
    for (int j = 0; j < 2; j++) {
        uint4 v = ldg128((const char*)g + j * 512 + lane * 16);
        gw[4 * j] = v.x; gw[4 * j + 1] = v.y; gw[4 * j + 2] = v.z; gw[4 * j + 3] = v.w;
        v = ldg128((const char*)b + j * 512 + lane * 16);
        bw[4 * j] = v.x; bw[4 * j + 1] = v.y; bw[4 * j + 2] = v.z; bw[4 * j + 3] = v.w;
    }
    gw[8] = ldg32((const char*)g + 1024 + lane * 4);
    bw[8] = ldg32((const char*)b + 1024 + lane * 4);
    const uint32_t a1 = *(const unsigned short*)alpha;
    const uint32_t a2 = a1 | (a1 << 16);
    char* po = (char*)out + (px - (const char*)x);

    while (true) {
        __syncwarp();
        auto axf = [&](uint32_t xv, uint32_t fv) { return hadd2(hmul2(a2, xv), fv); };
        uint32_t h[9];
        h[0] = axf(x0.x, f0.x); h[1] = axf(x0.y, f0.y); h[2] = axf(x0.z, f0.z); h[3] = axf(x0.w, f0.w);
        h[4] = axf(x1.x, f1.x); h[5] = axf(x1.y, f1.y); h[6] = axf(x1.z, f1.z); h[7] = axf(x1.w, f1.w);
        h[8] = axf(x2, f2);

        float a0 = lo_f32(h[0]), a3 = hi_f32(h[0]), q0 = a0 * a0, q1 = a3 * a3;
#pragma unroll
        for (int i = 1; i < 9; i++) {
            const float l = lo_f32(h[i]), u = hi_f32(h[i]);
            a0 += l; a3 += u; q0 = fmaf(l, l, q0); q1 = fmaf(u, u, q1);
        }
        float s1 = a0 + a3, s2 = q0 + q1;
#pragma unroll
        for (int m = 1; m < 32; m <<= 1) {
            s1 += __shfl_xor_sync(~0u, s1, m);
            s2 += __shfl_xor_sync(~0u, s2, m);
        }
        const float mean = s1 * (1.0f / D);
        const float ex2 = s2 * (1.0f / D);
        const float var = fmaf(-mean, mean, ex2);
        const uint32_t m2 = dup_bf16(mean);

        auto emit = [&](float v) {
            const float den = round_bf16(fast_sqrt(round_bf16(round_bf16(v) + 1e-5f)));
            const float rstd = fast_rcp(den);
            const uint32_t rh2 = dup_bf16(rstd);
            const uint32_t rl2 = dup_bf16(rstd - lo_f32(rh2));
            auto fin = [&](int i) {
                const uint32_t dm = hsub2(h[i], m2);
                const uint32_t q = hfma2(dm, rh2, hmul2(dm, rl2));
                return hadd2(hmul2(q, gw[i]), bw[i]);
            };
            stg128(po, make_uint4(fin(0), fin(1), fin(2), fin(3)));
            stg128(po + 512, make_uint4(fin(4), fin(5), fin(6), fin(7)));
            stg32(po + toff, fin(8));
        };
        emit(var);
        if (__builtin_expect(!(var * 32.f >= ex2 && ex2 <= 3.0e38f), 0)) {
            float r0 = 0.f, r1 = 0.f;
#pragma unroll
            for (int i = 0; i < 9; i++) {
                const float l = (lo_f32(h[i]) - mean) * 0.03125f, u = (hi_f32(h[i]) - mean) * 0.03125f;
                r0 = fmaf(l, l, r0); r1 = fmaf(u, u, r1);
            }
            float r = r0 + r1;
#pragma unroll
            for (int m = 1; m < 32; m <<= 1) r += __shfl_xor_sync(~0u, r, m);
            emit(r * (1024.0f / D));
        }

        row += NWARP * G;
        if (row >= rows) break;
        px += step; pf += step; po += step;
        due = min(due + NWARP * SLOT_CYCLES, due_max);
        while ((int)(clock() - t0) < due) { }
        x0 = ldg128_stream(px); f0 = ldg128_stream(pf);
        x1 = ldg128_stream(px + 512); f1 = ldg128_stream(pf + 512);
        x2 = ldg32_stream(px + toff); f2 = ldg32_stream(pf + toff);
    }
}

extern "C" void kernel_launch(void* const* d_in, const int* in_sizes, int n_in,
                              void* d_out, int out_size) {
    static int num_sms = 0;
    if (num_sms == 0) {
        int dev = 0;
        cudaGetDevice(&dev);
        cudaDeviceGetAttribute(&num_sms, cudaDevAttrMultiProcessorCount, dev);
        if (num_sms <= 0) num_sms = 132;
    }
    const unsigned rows = (unsigned)(in_sizes[0] / D);
    const unsigned G = (unsigned)num_sms;
    auto kern = (rows == 8192 && G == 132) ? deepnorm_kernel<8192, 132> : deepnorm_kernel<0, 0>;
    kern<<<G, NWARP * 32>>>((const bf16*)d_in[0], (const bf16*)d_in[1], (const bf16*)d_in[2],
                            (const bf16*)d_in[3], (const bf16*)d_in[4], (bf16*)d_out, rows, G);
}
```

```cpp
#include <cuda_runtime.h>
#include <cuda_bf16.h>
#include <stdint.h>

typedef __nv_bfloat16 bf16;

constexpr int D = 576;
constexpr unsigned ROW_VEC = D * 2 / 16;
constexpr int NWARP = 31;
constexpr int SLOT_CYCLES = 184;
constexpr int HEAD_CYCLES = 400;
constexpr unsigned HOLD_FIRST = 32;
constexpr unsigned SYNC_LAST = 51;
constexpr int RELEASE_CYCLES = 1000;

__device__ __forceinline__ uint4 ldg128(const void* p) {
    uint4 v;
    asm volatile("ld.global.nc.v4.u32 {%0,%1,%2,%3}, [%4];"
                 : "=r"(v.x), "=r"(v.y), "=r"(v.z), "=r"(v.w) : "l"(p));
    return v;
}
__device__ __forceinline__ uint32_t ldg32(const void* p) {
    uint32_t v;
    asm volatile("ld.global.nc.u32 %0, [%1];" : "=r"(v) : "l"(p));
    return v;
}
__device__ __forceinline__ uint4 ldg128_stream(const void* p) {
    uint4 v;
    asm volatile("ld.global.nc.L1::no_allocate.v4.u32 {%0,%1,%2,%3}, [%4];"
                 : "=r"(v.x), "=r"(v.y), "=r"(v.z), "=r"(v.w) : "l"(p));
    return v;
}
__device__ __forceinline__ uint32_t ldg32_stream(const void* p) {
    uint32_t v;
    asm volatile("ld.global.nc.L1::no_allocate.u32 %0, [%1];" : "=r"(v) : "l"(p));
    return v;
}
__device__ __forceinline__ void stg128(void* p, uint4 v) {
    asm volatile("st.global.v4.u32 [%0], {%1,%2,%3,%4};" :: "l"(p), "r"(v.x), "r"(v.y), "r"(v.z), "r"(v.w) : "memory");
}
__device__ __forceinline__ void stg32(void* p, uint32_t v) {
    asm volatile("st.global.u32 [%0], %1;" :: "l"(p), "r"(v) : "memory");
}
__device__ __forceinline__ uint32_t hfma2(uint32_t a, uint32_t b, uint32_t c) {
    uint32_t d; asm("fma.rn.bf16x2 %0, %1, %2, %3;" : "=r"(d) : "r"(a), "r"(b), "r"(c)); return d;
}
__device__ __forceinline__ uint32_t hmul2(uint32_t a, uint32_t b) {
    uint32_t d; asm("mul.rn.bf16x2 %0, %1, %2;" : "=r"(d) : "r"(a), "r"(b)); return d;
}
__device__ __forceinline__ uint32_t hadd2(uint32_t a, uint32_t b) {
    uint32_t d; asm("add.rn.bf16x2 %0, %1, %2;" : "=r"(d) : "r"(a), "r"(b)); return d;
}
__device__ __forceinline__ uint32_t hsub2(uint32_t a, uint32_t b) {
    uint32_t d; asm("sub.rn.bf16x2 %0, %1, %2;" : "=r"(d) : "r"(a), "r"(b)); return d;
}
__device__ __forceinline__ float lo_f32(uint32_t u) { return __uint_as_float(u << 16); }
__device__ __forceinline__ float hi_f32(uint32_t u) { return __uint_as_float(u & 0xffff0000u); }
__device__ __forceinline__ uint32_t dup_bf16(float v) {
    uint32_t d; asm("cvt.rn.bf16x2.f32 %0, %1, %1;" : "=r"(d) : "f"(v)); return d;
}
__device__ __forceinline__ float round_bf16(float v) {
    uint32_t d; asm("cvt.rn.bf16x2.f32 %0, %1, %2;" : "=r"(d) : "f"(v), "f"(0.f)); return __uint_as_float(d);
}
__device__ __forceinline__ float fast_sqrt(float v) { float d; asm("sqrt.approx.ftz.f32 %0, %1;" : "=f"(d) : "f"(v)); return d; }
__device__ __forceinline__ float fast_rcp(float v) { float d; asm("rcp.approx.ftz.f32 %0, %1;" : "=f"(d) : "f"(v)); return d; }

template <unsigned CROWS, unsigned CG>
__global__ void __launch_bounds__(NWARP * 32, 1)
deepnorm_kernel(const bf16* __restrict__ x, const bf16* __restrict__ f, const bf16* __restrict__ g,
                const bf16* __restrict__ b, const bf16* __restrict__ alpha, bf16* __restrict__ out,
                unsigned rows_rt, unsigned G_rt) {
    const unsigned rows = CROWS ? CROWS : rows_rt, G = CG ? CG : G_rt;
    constexpr bool HOLD = CROWS != 0;
    static_assert(!HOLD || ((SYNC_LAST + 1) * CG <= CROWS && (HOLD_FIRST + NWARP) * CG >= CROWS), "hold range");
    const unsigned lane = threadIdx.x & 31, warp = threadIdx.x >> 5;
    unsigned row = warp * G + blockIdx.x;
    const unsigned idx = row * ROW_VEC + lane;
    const char* px = (const char*)((const uint4*)x + idx);
    const char* pf = (const char*)((const uint4*)f + idx);
    const unsigned t0 = clock();
    const size_t step = (size_t)G * (NWARP * ROW_VEC * 16);
    const unsigned toff = 1024 - lane * 12;
    int due = (int)warp * SLOT_CYCLES - HEAD_CYCLES;
    const int due_max = max((int)(rows / G) * SLOT_CYCLES - SLOT_CYCLES - HEAD_CYCLES, 0);
    if (px == nullptr || pf == nullptr) return;
    if ((CROWS == 0 || CROWS < NWARP * CG) && row >= rows) return;

    auto wait_until = [&](int c) { while ((unsigned)clock() - t0 < (unsigned)c) { } };
    if (due > 0) wait_until(due);
    uint4 x0 = ldg128_stream(px), f0 = ldg128_stream(pf);
    uint4 x1 = ldg128_stream(px + 512), f1 = ldg128_stream(pf + 512);
    uint32_t x2 = ldg32_stream(px + toff), f2 = ldg32_stream(pf + toff);

    uint32_t gw[9], bw[9];
#pragma unroll
    for (int j = 0; j < 2; j++) {
        uint4 v = ldg128((const char*)g + j * 512 + lane * 16);
        gw[4 * j] = v.x; gw[4 * j + 1] = v.y; gw[4 * j + 2] = v.z; gw[4 * j + 3] = v.w;
        v = ldg128((const char*)b + j * 512 + lane * 16);
        bw[4 * j] = v.x; bw[4 * j + 1] = v.y; bw[4 * j + 2] = v.z; bw[4 * j + 3] = v.w;
    }
    gw[8] = ldg32((const char*)g + 1024 + lane * 4);
    bw[8] = ldg32((const char*)b + 1024 + lane * 4);
    const uint32_t a1 = *(const unsigned short*)alpha;
    const uint32_t a2 = a1 | (a1 << 16);
    char* po = (char*)out + (px - (const char*)x);

    while (true) {
        __syncwarp();
        auto axf = [&](uint32_t xv, uint32_t fv) { return hadd2(hmul2(a2, xv), fv); };
        uint32_t h[9];
        h[0] = axf(x0.x, f0.x); h[1] = axf(x0.y, f0.y); h[2] = axf(x0.z, f0.z); h[3] = axf(x0.w, f0.w);
        h[4] = axf(x1.x, f1.x); h[5] = axf(x1.y, f1.y); h[6] = axf(x1.z, f1.z); h[7] = axf(x1.w, f1.w);
        h[8] = axf(x2, f2);

        float a0 = lo_f32(h[0]), a3 = hi_f32(h[0]), q0 = a0 * a0, q1 = a3 * a3;
#pragma unroll
        for (int i = 1; i < 9; i++) {
            const float l = lo_f32(h[i]), u = hi_f32(h[i]);
            a0 += l; a3 += u; q0 = fmaf(l, l, q0); q1 = fmaf(u, u, q1);
        }
        float s1 = a0 + a3, s2 = q0 + q1;
#pragma unroll
        for (int m = 1; m < 32; m <<= 1) {
            s1 += __shfl_xor_sync(~0u, s1, m);
            s2 += __shfl_xor_sync(~0u, s2, m);
        }
        const float mean = s1 * (1.0f / D);
        const float ex2 = s2 * (1.0f / D);
        const float var = fmaf(-mean, mean, ex2);
        const uint32_t m2 = dup_bf16(mean);

        auto emit = [&](float v, bool may_hold) {
            const float den = round_bf16(fast_sqrt(round_bf16(round_bf16(v) + 1e-5f)));
            const float rstd = fast_rcp(den);
            const uint32_t rh2 = dup_bf16(rstd);
            const uint32_t rl2 = dup_bf16(rstd - lo_f32(rh2));
            uint32_t o[9];
#pragma unroll
            for (int i = 0; i < 9; i++) {
                const uint32_t dm = hsub2(h[i], m2);
                const uint32_t q = hfma2(dm, rh2, hmul2(dm, rl2));
                o[i] = hadd2(hmul2(q, gw[i]), bw[i]);
            }
            asm volatile("" :: "r"(o[0]), "r"(o[1]), "r"(o[2]), "r"(o[3]), "r"(o[4]), "r"(o[5]), "r"(o[6]),
                               "r"(o[7]), "r"(o[8]));
            if (may_hold && row >= HOLD_FIRST * G) {
                if (row < (SYNC_LAST + 1) * G)
                    asm volatile("bar.sync 1, %0;" :: "n"((SYNC_LAST - HOLD_FIRST + 1) * 32) : "memory");
                wait_until(due_max + RELEASE_CYCLES);
            }
            stg128(po, make_uint4(o[0], o[1], o[2], o[3]));
            stg128(po + 512, make_uint4(o[4], o[5], o[6], o[7]));
            stg32(po + toff, o[8]);
        };
        emit(var, HOLD);
        if (__builtin_expect(!(var * 32.f >= ex2 && ex2 <= 3.0e38f), 0)) {
            float r0 = 0.f, r1 = 0.f;
#pragma unroll
            for (int i = 0; i < 9; i++) {
                h[i] = __shfl_sync(~0u, h[i], lane);
                const float l = (lo_f32(h[i]) - mean) * 0.03125f, u = (hi_f32(h[i]) - mean) * 0.03125f;
                r0 = fmaf(l, l, r0); r1 = fmaf(u, u, r1);
            }
            float r = r0 + r1;
#pragma unroll
            for (int m = 1; m < 32; m <<= 1) r += __shfl_xor_sync(~0u, r, m);
            emit(r * (1024.0f / D), false);
        }

        row += NWARP * G;
        if (row >= rows) break;
        px += step; pf += step; po += step;
        due = min(due + NWARP * SLOT_CYCLES, due_max);
        wait_until(due);
        x0 = ldg128_stream(px); f0 = ldg128_stream(pf);
        x1 = ldg128_stream(px + 512); f1 = ldg128_stream(pf + 512);
        x2 = ldg32_stream(px + toff); f2 = ldg32_stream(pf + toff);
    }
}

extern "C" void kernel_launch(void* const* d_in, const int* in_sizes, int n_in,
                              void* d_out, int out_size) {
    static int num_sms = 0;
    if (num_sms == 0) {
        int dev = 0;
        cudaGetDevice(&dev);
        cudaDeviceGetAttribute(&num_sms, cudaDevAttrMultiProcessorCount, dev);
        if (num_sms <= 0) num_sms = 132;
    }
    const unsigned rows = (unsigned)(in_sizes[0] / D);
    const unsigned G = (unsigned)num_sms;
    auto kern = (rows == 8192 && G == 132) ? deepnorm_kernel<8192, 132> : deepnorm_kernel<0, 0>;
    kern<<<G, NWARP * 32>>>((const bf16*)d_in[0], (const bf16*)d_in[1], (const bf16*)d_in[2],
                            (const bf16*)d_in[3], (const bf16*)d_in[4], (bf16*)d_out, rows, G);
}
```
